```python
import torch

def _softmax(x, axis=-1):
    return torch.softmax(x, dim=axis)
def _gelu(x):
    return torch.nn.functional.gelu(x, approximate="tanh")
def _silu(x):
    return torch.nn.functional.silu(x)
def _sigmoid(x):
    return torch.sigmoid(x)
def _layernorm(x, axis=-1, eps=1e-5):
    m = x.mean(dim=axis, keepdim=True)
    v = x.var(dim=axis, keepdim=True, unbiased=False)
    return (x - m) / torch.sqrt(v + eps)
def _scatter_add(tgt, idx, src, axis=0):
    return tgt.clone().index_add_(axis, idx, src)
def _segment_sum(src, seg, n):
    out = torch.zeros((n,) + src.shape[1:], dtype=src.dtype)
    return out.index_add_(0, seg, src)
def _pad(x, pw):
    flat = tuple(v for pair in reversed(pw) for v in pair)
    return torch.nn.functional.pad(x, flat)

kernel_name = 'standalone__embedding_ops__recsys'

def setup_inputs():

    _w = (lambda a: (lambda t: t.to(torch.bfloat16) if t.is_floating_point() else t)(torch.as_tensor(a)))
    B, D = 16384, 128
    L = max(20, 2)
    V = min(100000, 100000)
    lengths = torch.randint(1, L + 1, (B,) if isinstance(B, int) else B)
    nnz = int(lengths.sum())
    seg = torch.repeat_interleave(torch.arange(B), lengths).to(torch.int64)
    vals = (lambda lo, hi, *s: torch.randint(lo, hi, s))(0, V, nnz).to(torch.int64)
    return {
        "values": _w(vals),
        "seg_ids": _w(seg),
        "table": _w((lambda *s: torch.randn(*s, dtype=torch.bfloat16) * 0.05)(V, D)),
        "out0": _w((lambda *s: torch.randn(*s, dtype=torch.bfloat16) * 0.05)(B, D)),
    }

def reference(values, seg_ids, table, out0):
    emb = table[values]
    n_seg = out0.shape[0]
    pooled = _segment_sum(emb, seg_ids, n_seg)
    return pooled + out0
```

```cpp
#include <cuda_runtime.h>
#include <cuda_bf16.h>
#include <stdint.h>

namespace v4 {
__device__ unsigned g_ts[16384 * 8];
__device__ __forceinline__ unsigned gt32() { unsigned t; asm volatile("mov.u32 %0, %%globaltimer_lo;" : "=r"(t)); return t; }
__device__ __forceinline__ float lo(uint32_t x) { return __uint_as_float(x << 16); }
__device__ __forceinline__ float hi(uint32_t x) { return __uint_as_float(x & 0xffff0000u); }
__device__ __forceinline__ uint32_t pack2(float a, float b) { uint32_t r; asm("cvt.rn.bf16x2.f32 %0, %1, %2;" : "=r"(r) : "f"(b), "f"(a)); return r; }
__device__ __forceinline__ uint32_t addbf2(uint32_t a, uint32_t b) { uint32_t r; asm("add.rn.bf16x2 %0, %1, %2;" : "=r"(r) : "r"(a), "r"(b)); return r; }
__device__ __forceinline__ uint2 fin(const float4& a, uint2 o) { return make_uint2(addbf2(pack2(a.x, a.y), o.x), addbf2(pack2(a.z, a.w), o.y)); }
__device__ __forceinline__ void addrow(float4& a, uint2 r) { a.x += lo(r.x); a.y += hi(r.x); a.z += lo(r.y); a.w += hi(r.y); }
__device__ __forceinline__ uint2 ldrow(const char* base, int it) {
    uint2 r;
    asm volatile("{ .reg .u64 a; mad.wide.s32 a, %2, 256, %3; ld.global.nc.v2.u32 {%0,%1}, [a]; }" : "=r"(r.x), "=r"(r.y) : "r"(it), "l"(base));
    return r;
}
__device__ __forceinline__ uint2 ldbag(const char* base, int b, int l8) {
    uint2 r;
    asm volatile("ld.global.nc.v2.u32 {%0,%1}, [%2];" : "=r"(r.x), "=r"(r.y) : "l"(base + (unsigned)(b * 256 + l8)));
    return r;
}
__device__ __forceinline__ void stbag(char* base, int b, int l8, uint2 v) {
    asm volatile("st.global.v2.u32 [%0], {%1,%2};" :: "l"(base + (unsigned)(b * 256 + l8)), "r"(v.x), "r"(v.y) : "memory");
}
__device__ __forceinline__ void cpbag(uint32_t dst, const char* base, int b, int l8) {
    asm volatile("cp.async.ca.shared.global [%0], [%1], 8;" :: "r"(dst), "l"(base + (unsigned)(b * 256 + l8)) : "memory");
}
__device__ __forceinline__ int ldi(const int* p, bool ok, int dflt) {
    int r = dflt;
    asm volatile("{ .reg .pred p; setp.ne.s32 p, %2, 0; @p ld.global.nc.s32 %0, [%1]; }" : "+r"(r) : "l"(p), "r"((int)ok));
    return r;
}
__device__ __forceinline__ uint2 lds64(uint32_t a) { uint2 r; asm volatile("ld.shared.v2.u32 {%0,%1}, [%2];" : "=r"(r.x), "=r"(r.y) : "r"(a) : "memory"); return r; }
__device__ __forceinline__ float4 lds128(uint32_t a) { float4 r; asm volatile("ld.shared.v4.f32 {%0,%1,%2,%3}, [%4];" : "=f"(r.x), "=f"(r.y), "=f"(r.z), "=f"(r.w) : "r"(a) : "memory"); return r; }
__device__ __forceinline__ void sts128(uint32_t a, float4 v) { asm volatile("st.shared.v4.f32 [%0], {%1,%2,%3,%4};" :: "r"(a), "f"(v.x), "f"(v.y), "f"(v.z), "f"(v.w) : "memory"); }
__device__ __forceinline__ void mbar_arrive(uint32_t bar) { asm volatile("mbarrier.arrive.release.cta.shared::cta.b64 _, [%0];" :: "r"(bar) : "memory"); }
__device__ __forceinline__ void mbar_wait0(uint32_t bar) {
    asm volatile("{\n.reg .pred p;\nW%=:\nmbarrier.try_wait.parity.acquire.cta.shared::cta.b64 p, [%0], 0;\n@!p bra W%=;\n}" :: "r"(bar) : "memory");
}

template <int W, int U, int MINB, int TS>
__global__ void __launch_bounds__(W * 32, MINB) k(const int* __restrict__ vals, const int* __restrict__ seg, const char* __restrict__ table,
                  const char* __restrict__ out0, char* __restrict__ out, int nnz, int B) {
    constexpr int WB = U * 256 + 512 + 16;
    extern __shared__ __align__(16) char smem[];
    unsigned t0, t1; if (TS) t0 = gt32();
    const int lane = threadIdx.x & 31, w = __shfl_sync(~0u, threadIdx.x >> 5, 0);
    const int a = (blockIdx.x * (W - 1) + w) * 32;
    const int p = a + lane;
    int v = ldi(vals + p, p < nnz, 0);
    const int s = ldi(seg + p, p < nnz, B);
    const int sp = ldi(seg + a - 1, a > 0 && a <= nnz, -1);
    const int sn = ldi(seg + a + 32, a + 32 < nnz, B);
    const uint32_t sw = (uint32_t)__cvta_generic_to_shared(smem) + w * WB;
    if (lane == 0) asm volatile("mbarrier.init.shared::cta.b64 [%0], 32;" :: "r"(sw + U * 256 + 512) : "memory");
    __syncthreads();
    if (a >= nnz) return;
    const char* tl = table + lane * 8;
    const int l8 = lane * 8;
    const uint32_t slot = sw + lane * 8, cw = sw + U * 256 + lane * 16;
    float4 acc = make_float4(0, 0, 0, 0);

    if (w == W - 1) {
        const int bPrev = ldi(seg + a - (W - 1) * 32 - 1, blockIdx.x > 0, -1);
        if (bPrev == sp) return;
        int ss = s, q = p;
        while (true) {
            int n = __popc(__ballot_sync(~0u, ss == sp));
            for (int j = 0; j < n; j += 4) {
                uint2 r[4];
                #pragma unroll
                for (int u = 0; u < 4; u++) { int it = __shfl_sync(~0u, v, min(j + u, n - 1)); r[u] = ldrow(tl, it); }
                #pragma unroll
                for (int u = 0; u < 4; u++) if (j + u < n) addrow(acc, r[u]);
            }
            if (n < 32) break;
            q += 32;
            ss = ldi(seg + q, q < nnz, B); v = ldi(vals + q, q < nnz, 0);
        }
        sts128(cw, acc);
        if (lane == 0) asm volatile("st.shared.u32 [%0], %1;" :: "r"(sw + U * 256 + 512 + 8), "r"(0) : "memory");
        mbar_arrive(sw + U * 256 + 512);
        return;
    }
    if (w == 0) {
        int vl = __shfl_sync(~0u, v, 31);
        if (s == sp) v = vl;
    }
    uint2 r[U];
    #pragma unroll
    for (int u = 0; u < U; u++) r[u] = ldrow(tl, __shfl_sync(~0u, v, u));
    if (TS) t1 = gt32();

    int n0 = __shfl_down_sync(~0u, s, 1);
    if (lane == 31) n0 = sn;
    const unsigned mt = __ballot_sync(~0u, n0 != s);
    const int s0 = __shfl_sync(~0u, s, 0), s31 = __shfl_sync(~0u, s, 31);
    bool lead = sp == s0;
    const bool own_trail = (int)mt >= 0 && (mt != 0 || !lead) && s31 < B;
    unsigned mo = lead ? (mt & (mt - 1)) : mt;
    {
        unsigned g = __ballot_sync(~0u, n0 - s > 1);
        if (__builtin_expect(g != 0 || a == 0, 0)) {
            if (a == 0) { _Pragma("unroll 1") for (int b = 0; b < s0; b++) stbag(out, b, l8, fin(make_float4(0,0,0,0), ldbag(out0, b, l8))); }
            while (g) {
                int l = __ffs(g) - 1; g &= g - 1;
                int b = __shfl_sync(~0u, s, l) + 1, e = __shfl_sync(~0u, n0, l);
                _Pragma("unroll 1") for (; b < e; b++) stbag(out, b, l8, fin(make_float4(0,0,0,0), ldbag(out0, b, l8)));
            }
        }
    }
    uint2 otr = make_uint2(0, 0);
    #pragma unroll
    for (int j = 0; j < 32; j += U) {
        if (j > 0) {
            #pragma unroll
            for (int u = 0; u < U; u++) r[u] = ldrow(tl, __shfl_sync(~0u, v, j + u));
        }
        for (unsigned m = (mo >> j) & ((1u << U) - 1); m; m &= m - 1) {
            int u = __ffs(m) - 1;
            cpbag(slot + u * 256, out0, __shfl_sync(~0u, s, j + u), l8);
        }
        if (j + U >= 32 && own_trail) otr = ldbag(out0, s31, l8);
        const unsigned m = mt >> j;
        #pragma unroll
        for (int u = 0; u < U; u++) {
            addrow(acc, r[u]);
            if (__builtin_expect((m & (1u << u)) != 0, 0)) {
                if (lead) {
                    sts128(cw, acc);
                    if (lane == 0) asm volatile("st.shared.u32 [%0], %1;" :: "r"(sw + U * 256 + 512 + 8), "r"(0) : "memory");
                    mbar_arrive(sw + U * 256 + 512);
                    lead = false;
                } else {
                    int b = __shfl_sync(~0u, s, j + u);
                    asm volatile("cp.async.wait_all;" ::: "memory");
                    stbag(out, b, l8, fin(acc, lds64(slot + u * 256)));
                }
                acc = make_float4(0, 0, 0, 0);
            }
        }
    }
    if (lead) {
        sts128(cw, acc);
        if (lane == 0) asm volatile("st.shared.u32 [%0], %1;" :: "r"(sw + U * 256 + 512 + 8), "r"(1) : "memory");
        mbar_arrive(sw + U * 256 + 512);
    }
    if (own_trail) {
        uint32_t o = WB;
        while (true) {
            mbar_wait0(sw + o + U * 256 + 512);
            float4 c = lds128(cw + o);
            int more; asm volatile("ld.shared.u32 %0, [%1];" : "=r"(more) : "r"(sw + o + U * 256 + 512 + 8) : "memory");
            acc.x += c.x; acc.y += c.y; acc.z += c.z; acc.w += c.w;
            if (!more) break;
            o += WB;
        }
        stbag(out, s31, l8, fin(acc, otr));
    }
    if (TS) { unsigned t3 = gt32(); int gw = a / 32; if (lane == 0) { g_ts[gw * 4] = t0; g_ts[gw * 4 + 1] = t1; g_ts[gw * 4 + 2] = t3; g_ts[gw * 4 + 3] = 0; } }
}

__global__ void k_empty(const uint2* __restrict__ out0, uint2* __restrict__ out, int n) {
    for (int i = blockIdx.x * blockDim.x + threadIdx.x; i < n; i += gridDim.x * blockDim.x) out[i] = fin(make_float4(0, 0, 0, 0), out0[i]);
}
template <int W, int U, int MINB, int TS>
void launch(void* const* d_in, const int* sz, int, void* d_out, int out_size) {
    int nnz = sz[0], B = out_size / 128;
    if (nnz == 0) { k_empty<<<256, 256, 0, cudaStreamPerThread>>>((const uint2*)d_in[3], (uint2*)d_out, B * 32); return; }
    int warps = (nnz + 31) / 32;
    int G = (warps + W - 2) / (W - 1);
    constexpr int smem = W * (U * 256 + 512 + 16);
    static bool init = false;
    if (!init) { cudaFuncSetAttribute(k<W, U, MINB, TS>, cudaFuncAttributeMaxDynamicSharedMemorySize, smem); init = true; }
    k<W, U, MINB, TS><<<G, W * 32, smem, cudaStreamPerThread>>>((const int*)d_in[0], (const int*)d_in[1], (const char*)d_in[2], (const char*)d_in[3], (char*)d_out, nnz, B);
}
}

extern "C" void kernel_launch(void* const* d_in, const int* in_sizes, int n_in, void* d_out, int out_size) {
    v4::launch<15, 8, 3, 0>(d_in, in_sizes, n_in, d_out, out_size);
}
```

```cpp
#include <cuda_runtime.h>
#include <cuda_bf16.h>
#include <stdint.h>

namespace {

__device__ unsigned g_started;

__device__ __forceinline__ uint32_t pack2(float a, float b) { uint32_t r; asm("cvt.rn.bf16x2.f32 %0, %1, %2;" : "=r"(r) : "f"(b), "f"(a)); return r; }
__device__ __forceinline__ uint32_t addbf2(uint32_t a, uint32_t b) { uint32_t r; asm("add.rn.bf16x2 %0, %1, %2;" : "=r"(r) : "r"(a), "r"(b)); return r; }
__device__ __forceinline__ uint2 fin(const float4& a, uint2 o) { return make_uint2(addbf2(pack2(a.x, a.y), o.x), addbf2(pack2(a.z, a.w), o.y)); }
__device__ __forceinline__ void addrow(float4& acc, uint2 r) {
    acc.x += __uint_as_float(r.x << 16); acc.y += __uint_as_float(r.x & 0xffff0000u);
    acc.z += __uint_as_float(r.y << 16); acc.w += __uint_as_float(r.y & 0xffff0000u);
}
__device__ __forceinline__ int lds32(uint32_t a) { int r; asm volatile("ld.shared.u32 %0, [%1];" : "=r"(r) : "r"(a) : "memory"); return r; }
__device__ __forceinline__ uint2 lds64(uint32_t a) { uint2 r; asm volatile("ld.shared.v2.u32 {%0,%1}, [%2];" : "=r"(r.x), "=r"(r.y) : "r"(a) : "memory"); return r; }
__device__ __forceinline__ int4 lds128i(uint32_t a) { int4 r; asm volatile("ld.shared.v4.u32 {%0,%1,%2,%3}, [%4];" : "=r"(r.x), "=r"(r.y), "=r"(r.z), "=r"(r.w) : "r"(a) : "memory"); return r; }
__device__ __forceinline__ float4 lds128(uint32_t a) { float4 r; asm volatile("ld.shared.v4.f32 {%0,%1,%2,%3}, [%4];" : "=f"(r.x), "=f"(r.y), "=f"(r.z), "=f"(r.w) : "r"(a) : "memory"); return r; }
__device__ __forceinline__ float4 lds128_if(uint32_t a, bool ok) { float4 r; asm volatile("{ .reg .pred p; setp.ne.s32 p, %5, 0; @p ld.shared.v4.f32 {%0,%1,%2,%3}, [%4]; }" : "=f"(r.x), "=f"(r.y), "=f"(r.z), "=f"(r.w) : "r"(a), "r"((int)ok) : "memory"); return r; }
__device__ __forceinline__ uint2 lds64_if(uint32_t a, bool ok) { uint2 r; asm volatile("{ .reg .pred p; setp.ne.s32 p, %3, 0; @p ld.shared.v2.u32 {%0,%1}, [%2]; }" : "=r"(r.x), "=r"(r.y) : "r"(a), "r"((int)ok) : "memory"); return r; }
__device__ __forceinline__ void sts32(uint32_t a, int v) { asm volatile("st.shared.u32 [%0], %1;" :: "r"(a), "r"(v) : "memory"); }
__device__ __forceinline__ void sts64(uint32_t a, uint2 v) { asm volatile("st.shared.v2.u32 [%0], {%1,%2};" :: "r"(a), "r"(v.x), "r"(v.y) : "memory"); }
__device__ __forceinline__ void sts128i(uint32_t a, int4 v) { asm volatile("st.shared.v4.u32 [%0], {%1,%2,%3,%4};" :: "r"(a), "r"(v.x), "r"(v.y), "r"(v.z), "r"(v.w) : "memory"); }
__device__ __forceinline__ void sts128(uint32_t a, float4 v) { asm volatile("st.shared.v4.f32 [%0], {%1,%2,%3,%4};" :: "r"(a), "f"(v.x), "f"(v.y), "f"(v.z), "f"(v.w) : "memory"); }
__device__ __forceinline__ void sts2p(uint32_t a, const void* x, const void* y) { asm volatile("st.shared.v2.u64 [%0], {%1,%2};" :: "r"(a), "l"(x), "l"(y) : "memory"); }
__device__ __forceinline__ void ldg2(uint2& r0, uint2& r1, int4 a, uint32_t lo) {
    asm volatile("{ .reg .u32 a0,a2; .reg .u64 p,q;\n"
        "or.b32 a0, %4, %8; or.b32 a2, %6, %8;\n"
        "mov.b64 p, {a0,%5}; mov.b64 q, {a2,%7};\n"
        "ld.global.nc.v2.u32 {%0,%1}, [p];\n"
        "ld.global.nc.v2.u32 {%2,%3}, [q]; }"
        : "=r"(r0.x), "=r"(r0.y), "=r"(r1.x), "=r"(r1.y) : "r"(a.x), "r"(a.y), "r"(a.z), "r"(a.w), "r"(lo) : "memory");
}
__device__ __forceinline__ uint2 ldg8(const char* p) { uint2 r; asm volatile("ld.global.nc.v2.u32 {%0,%1}, [%2];" : "=r"(r.x), "=r"(r.y) : "l"(p)); return r; }
__device__ __forceinline__ void stg8_if(char* p, uint2 v, bool ok) {
    asm volatile("{ .reg .pred p; setp.ne.s32 p, %3, 0; @p st.global.v2.u32 [%0], {%1,%2}; }" :: "l"(p), "r"(v.x), "r"(v.y), "r"((int)ok) : "memory");
}
__device__ __forceinline__ void cp8_if(uint32_t dst, const char* src, bool ok) {
    asm volatile("{ .reg .pred p; setp.ne.s32 p, %2, 0; @p cp.async.ca.shared.global [%0], [%1], 8; }" :: "r"(dst), "l"(src), "r"((int)ok) : "memory");
}
__device__ __forceinline__ void cp_wait_all() { asm volatile("cp.async.wait_all;" ::: "memory"); }
__device__ __forceinline__ void cp_commit() { asm volatile("cp.async.commit_group;" ::: "memory"); }
__device__ __forceinline__ void cp_wait0() { asm volatile("cp.async.wait_group 0;" ::: "memory"); }
__device__ __forceinline__ void mbar_arrive(uint32_t bar) { asm volatile("mbarrier.arrive.release.cta.shared::cta.b64 _, [%0];" :: "r"(bar) : "memory"); }
__device__ __forceinline__ void mbar_wait0(uint32_t bar) {
    asm volatile("{\n.reg .pred p; .reg .u32 n;\nmov.u32 n, 0;\nW%=:\nmbarrier.try_wait.parity.acquire.cta.shared::cta.b64 p, [%0], 0, 100;\n@p bra D%=;\n"
                 "add.u32 n, n, 1;\nsetp.lt.u32 p, n, 0x4000000;\n@p bra W%=;\ntrap;\nD%=:\n}" :: "r"(bar) : "memory");
}
__device__ __forceinline__ unsigned sched_fence() { unsigned t; asm volatile("mov.u32 %0, %%clock;" : "=r"(t) :: "memory"); return t; }

template <unsigned BIT, int PS> __device__ __forceinline__ void step(float4& acc, uint32_t& pk, unsigned m, uint2 r) {
    float4 t;
    asm volatile("{ .reg .pred p; .reg .b32 t0,t1,t2,t3,x;\n"
        "and.b32 x, %11, %12; setp.ne.u32 p, x, 0;\n"
        "shl.b32 t0, %9, 16; and.b32 t1, %9, 0xffff0000; shl.b32 t2, %10, 16; and.b32 t3, %10, 0xffff0000;\n"
        "mov.b32 %0, t0; mov.b32 %1, t1; mov.b32 %2, t2; mov.b32 %3, t3;\n"
        "@p st.shared.v4.f32 [%4], {%5,%6,%7,%8};\n"
        "@p add.u32 %4, %4, %13;\n"
        "@!p add.f32 %0, %0, %5; @!p add.f32 %1, %1, %6; @!p add.f32 %2, %2, %7; @!p add.f32 %3, %3, %8; }"
        : "=&f"(t.x), "=&f"(t.y), "=&f"(t.z), "=&f"(t.w), "+r"(pk)
        : "f"(acc.x), "f"(acc.y), "f"(acc.z), "f"(acc.w), "r"(r.x), "r"(r.y), "r"(m), "n"(BIT), "n"(PS) : "memory");
    acc = t;
}
constexpr int kGroups = 8;
__host__ __device__ constexpr int gsize(int g) { constexpr int z[kGroups] = {8, 2, 8, 2, 10, 4, 10, 8}; return z[g]; }
__host__ __device__ constexpr int gstart(int g) { return g == 0 ? 0 : gstart(g - 1) + gsize(g - 1); }
__host__ __device__ constexpr int gmax(int g) { return g >= kGroups ? 0 : (gsize(g) > gmax(g + 2) ? gsize(g) : gmax(g + 2)); }

template <int U, int ROW, int N, int NEXT, int NR, int PS, int I = 0>
__device__ __forceinline__ void consume(float4& acc, uint32_t& pk, unsigned mlo, unsigned mhi, uint2 (&r)[U], uint32_t la, uint32_t lo,
                                        unsigned& keep, unsigned zero, int4 adn = int4()) {
    if constexpr (I < N || I < NR) {
        int4 ad = adn;
        if constexpr (I < NR && I == 0) ad = lds128i(la + NEXT * 8);
        if constexpr (I + 2 < NR) adn = lds128i(la + (NEXT + I + 2) * 8);
        uint32_t lo2 = lo;
        if constexpr (I == 0 && N > 0 && NR > 0) lo2 |= r[0].x & zero;
        if constexpr (I < N) {
            step<(1u << ((ROW + I) & 31)), PS>(acc, pk, ROW + I < 32 ? mlo : mhi, r[I]);
            step<(2u << ((ROW + I) & 31)), PS>(acc, pk, ROW + I < 32 ? mlo : mhi, r[I + 1]);
        }
        if constexpr (I < NR) ldg2(r[I], r[I + 1], ad, lo2);
        if constexpr (I < NR && (I < N || I + 2 >= NR)) keep ^= sched_fence();
        consume<U, ROW, N, NEXT, NR, PS, I + 2>(acc, pk, mlo, mhi, r, la, lo, keep, zero, adn);
    }
}
__device__ __forceinline__ void block_end(unsigned& keep, unsigned zero) {
    asm volatile("{\n.reg .pred p; .reg .u32 t;\nsetp.ne.u32 p, %1, 0;\nL%=:\nmov.u32 t, %%clock;\nxor.b32 %0, %0, t;\n@p bra L%=;\n}" : "+r"(keep) : "r"(zero) : "memory");
}
template <int UX, int UY, int PS, int G, class A>
__device__ __forceinline__ void rounds(float4& acc, uint32_t& pk, unsigned mlo, unsigned mhi, uint2 (&x)[UX], uint2 (&y)[UY], uint32_t la, uint32_t lo,
                                       unsigned& keep, unsigned zero, A& arrive_if) {
    consume<UY, 0, 0, gstart(G + 1), gsize(G + 1), PS>(acc, pk, mlo, mhi, y, la, lo, keep, zero);
    if constexpr (G + 2 < kGroups) {
        consume<UX, gstart(G), gsize(G), gstart(G + 2), gsize(G + 2), PS>(acc, pk, mlo, mhi, x, la, lo, keep, zero);
        consume<UY, gstart(G + 1), gsize(G + 1), 0, 0, PS>(acc, pk, mlo, mhi, y, la, lo, keep, zero);
        arrive_if();
        block_end(keep, zero & (1u << G));
        rounds<UX, UY, PS, G + 2>(acc, pk, mlo, mhi, x, y, la, lo, keep, zero, arrive_if);
    }
}

__device__ __forceinline__ void simple_bags(const int* vals, const int* seg, const char* table, int B, int nnz,
                                            const char* out0, char* out, int b0, int stride) {
    const int lo = (threadIdx.x & 31) * 8;
    for (int b = b0; b < B; b += stride) {
        int l = 0, hi = nnz;
        while (l < hi) { const int m = (unsigned)(l + hi) >> 1; if (seg[m] < b) l = m + 1; else hi = m; }
        float4 a = make_float4(0, 0, 0, 0);
        for (; l < nnz && seg[l] == b; l++) addrow(a, ldg8(table + (size_t)vals[l] * 256 + lo));
        stg8_if(out + (size_t)b * 256 + lo, fin(a, ldg8(out0 + (size_t)b * 256 + lo)), true);
    }
}

template <int NS, int WW, int CH, int NP> struct Layout {
    static constexpr int LPS = 32 / NS, PS = LPS * 16, OS = LPS * 8;
    static constexpr int OFF_S = NS * CH * 8 < 512 ? 512 : NS * CH * 8;
    static constexpr int OFF_M = OFF_S + (NS * CH + 8) * 4, WB = OFF_M + NS * 16;
    static constexpr int OFF_O = (WW * WB + 127) / 128 * 128, OFF_P = OFF_O + NP * OS, TOTAL = OFF_P + NP * PS;
};

constexpr int kSplitSMs = 132;
constexpr unsigned long long kHalfOfTpc = 0x28f1e3c78e8e8e8eull;

template <int NS, int W, int CH, int NP>
__global__ void __launch_bounds__(W * 32, 1)
embag_kernel(const int* __restrict__ vals, const int* __restrict__ seg, unsigned nnz3, unsigned ratio,
             const char* __restrict__ table, int B, int nnz, const char* __restrict__ out0, char* __restrict__ out, unsigned zero) {
    using LL = Layout<NS, W - 1, CH, NP>;
    constexpr int LPS = LL::LPS, PS = LL::PS, OS = LL::OS, OFF_S = LL::OFF_S, OFF_M = LL::OFF_M, WB = LL::WB;
    constexpr int NV = NS * CH / 4;
    constexpr int F = gsize(0), U = gmax(0), R = gsize(kGroups - 2) + gsize(kGroups - 1);
    static_assert(gstart(kGroups) == CH && kGroups % 2 == 0, "");
    static_assert(CH % 4 == 0 && CH > 32 && CH <= 56 && NV + 2 <= 32, "");
    extern __shared__ __align__(128) char smem[];

    const int lane = threadIdx.x & 31;
    const uint32_t sb = (uint32_t)__cvta_generic_to_shared(smem);
    const uint32_t wslot = sb + (threadIdx.x >> 5) * WB + OFF_S + lane * 16;
    const bool slane = lane < NV + 2;
    const int voff = (threadIdx.x >> 5) * (NS * CH) + lane * 4;
    const bool vok = lane < NV && threadIdx.x < (W - 1) * 32, sok = slane && threadIdx.x < (W - 1) * 32;
    unsigned job = blockIdx.x, half = 0;
    int st0;
    if constexpr (NS == 2) {
        unsigned id; asm volatile("mov.u32 %0, %%smid;" : "=r"(id));
        uint64_t x; asm("shr.b64 %0, %1, %2;" : "=l"(x) : "l"(kHalfOfTpc), "r"(id >> 1));
        const unsigned above = __popcll(x);
        half = (unsigned)x & 1;
        job = (half ? above - 1 : kSplitSMs / 2 - 1 - (id >> 1) - above) * 2 + (id & 1);
        st0 = (job * ratio) >> 16;
    } else st0 = (int)(((uint64_t)job * ratio) >> 16);
    const int P0 = st0 * CH;
    const int pv = P0 + voff;
    const int ps = pv - 4;
    int4 v = make_int4(0, 0, 0, 0);
    const char *vp, *sp;
    bool vin, gin;
    if constexpr (NS == 2) {
        unsigned off = st0 * (CH * 4) + voff * 4;
        asm("" : "+r"(off));
        vp = (const char*)vals + off; sp = (const char*)seg + off - 16;
        vin = off < nnz3; gin = off - 16 < nnz3;
    } else {
        const char* vb = (const char*)(vals + P0);
        const char* sgb = (const char*)(seg + P0 - 4);
        asm("" : "+l"(vb), "+l"(sgb));
        vp = vb + (unsigned)(voff * 4); sp = sgb + (unsigned)(voff * 4);
        vin = (unsigned)pv < nnz3; gin = (unsigned)ps < nnz3;
    }
    asm volatile("{ .reg .pred p; setp.ne.s32 p, %5, 0; @p ld.global.v4.s32 {%0,%1,%2,%3}, [%4]; }"
                 : "+r"(v.x), "+r"(v.y), "+r"(v.z), "+r"(v.w) : "l"(vp), "r"((int)(vok && vin)) : "memory");
    asm volatile("{ .reg .pred p; setp.ne.s32 p, %2, 0; @p cp.async.ca.shared.global [%0], [%1], 16; }"
                 :: "r"(wslot), "l"(sp), "r"((int)(sok && gin)) : "memory");
    unsigned keep = sched_fence();
    const int w = __shfl_sync(~0u, threadIdx.x >> 5, 0);
    const uint32_t sw = sb + w * WB;
    if constexpr (NS == 2) {
        unsigned nsm; asm volatile("mov.u32 %0, %%nsmid;" : "=r"(nsm));
        if (__builtin_expect(nsm != kSplitSMs, 0)) {
            cp_wait_all();
            simple_bags(vals, seg, table, B, nnz, out0, out, blockIdx.x * W + w, kSplitSMs * W);
            if (B < 0) sts32(sb, v.x ^ keep);
            return;
        }
    }
    if (w == W - 1) {
        if (lane == 0) {
            #pragma unroll
            for (int i = 0; i < (W - 1) * NS; i++)
                asm volatile("mbarrier.init.shared::cta.b64 [%0], %1;" :: "r"(sb + (i / NS) * WB + OFF_M + (i % NS) * 16), "n"(LPS) : "memory");
        }
        __syncwarp();
        asm volatile("barrier.arrive 0, %0;" :: "n"(W * 32) : "memory");
        if (NS == 2) {
            __nanosleep(2000);
            if (lane == 0)
                asm volatile("{\n.reg .pred p; .reg .u32 n, x;\natom.relaxed.gpu.global.inc.u32 x, [%0], %1;\nsetp.eq.u32 p, x, %1;\n@p bra D%=;\nmov.u32 n, 0;\n"
                             "W%=:\nnanosleep.u32 500;\nld.relaxed.gpu.global.u32 x, [%0];\nsetp.eq.u32 p, x, 0;\n@p bra D%=;\n"
                             "add.u32 n, n, 1;\nsetp.lt.u32 p, n, 0x400000;\n@p bra W%=;\ntrap;\nD%=:\n}" :: "l"(&g_started), "r"(gridDim.x - 1) : "memory");
        }
        return;
    }
    if (pv + 3 >= nnz) {
        if (slane && ps + 3 >= nnz && ps < nnz && ps >= 0)
            for (int i = 0; i < 4; i++) asm volatile("cp.async.ca.shared.global [%0], [%1], 4;" :: "r"(wslot + i * 4), "l"(seg + min(ps + i, nnz - 1)) : "memory");
        if (pv < nnz && lane < NV)
            for (int i = 0; i < 4; i++) asm volatile("cp.async.ca.shared.global [%0], [%1], 4;" :: "r"(sw + i * 4), "l"(vals + min(pv + i, nnz - 1)) : "memory");
    }
    cp_commit();
    const int nreg = (int)(((uint64_t)(job + 1) * ratio) >> 16) - st0;
    const int wa = P0 + w * NS * CH;
    if (w * NS > nreg || wa >= nnz) { asm volatile("barrier.arrive 0, %0;" :: "n"(W * 32) : "memory"); cp_wait_all(); return; }
    const int h = NS == 2 ? lane >> 4 : 0, ll = lane & (LPS - 1), t = w * NS + h;
    if (wa + NS * CH > nnz) {
        cp_wait_all();
        if (pv + 3 >= nnz && pv < nnz && lane < NV) v = lds128i(sw);
        __syncwarp();
    }

    const uint32_t lo = half * 128 + ll * 8;
    const uint32_t la = sw + (t > nreg ? 0 : h * CH * 8);
    uint2 r[U];
    {
        const char* tl = table + lo;
        const int src = t > nreg ? 0 : h * (CH / 4);
        #pragma unroll
        for (int u = 0; u < F; u++) {
            const int ix = __shfl_sync(~0u, (u & 3) == 0 ? v.x : (u & 3) == 1 ? v.y : (u & 3) == 2 ? v.z : v.w, src + u / 4);
            asm volatile("{ .reg .u64 a; mad.wide.s32 a, %2, 256, %3; ld.global.nc.v2.u32 {%0,%1}, [a]; }" : "=r"(r[u].x), "=r"(r[u].y) : "r"(ix), "l"(tl));
        }
    }
    keep ^= sched_fence();
    if (lane < NV) {
        sts2p(sw + lane * 32, table + (size_t)v.x * 256, table + (size_t)v.y * 256);
        sts2p(sw + lane * 32 + 16, table + (size_t)v.z * 256, table + (size_t)v.w * 256);
    }

    cp_wait0();
    if (wa == 0 || wa + NS * CH + 4 > nnz) {
        int4 x = lds128i(slane ? wslot : sw);
        if (ps < 0) x = make_int4(-1, -1, -1, -1);
        if (ps + 0 >= nnz) x.x = B;
        if (ps + 1 >= nnz) x.y = B;
        if (ps + 2 >= nnz) x.z = B;
        if (ps + 3 >= nnz) x.w = B;
        if (slane) sts128i(wslot, x);
    }
    asm volatile("barrier.sync 0, %0;" :: "n"(W * 32) : "memory");
    const uint32_t swin = sw + OFF_S + h * CH * 4;
    uint64_t mt;
    {
        const int4 x = lds128i(swin + (lane & 15) * 16); const int y = lds32(swin + (lane & 15) * 16 + 16);
        unsigned nib = (x.x != x.y) | (x.y != x.z) << 1 | (x.z != x.w) << 2 | (x.w != y) << 3;
        nib <<= (lane & 7) * 4;
        nib |= __shfl_xor_sync(~0u, nib, 1); nib |= __shfl_xor_sync(~0u, nib, 2); nib |= __shfl_xor_sync(~0u, nib, 4);
        const unsigned oth = __shfl_xor_sync(~0u, nib, 8);
        mt = ((lane & 8) ? ((uint64_t)nib << 32 | oth) : ((uint64_t)oth << 32 | nib)) >> 3;
    }
    bool lead = !(mt & 1);
    mt &= (2ull << CH) - 2;
    const int sfirst = lds32(swin + 16), slast = lds32(swin + 12 + CH * 4), snext = lds32(swin + 16 + CH * 4);
    const int bPrev = lds32(sb + OFF_S + 12);
    int nt = __popcll(mt);
    bool own = !(mt >> CH) && (nt != 0 || !lead) && slast < B;
    bool odd = snext - sfirst != nt || (wa + h == 0 && sfirst != 0);
    int Kn = nt - lead + own;
    if (t >= nreg || sfirst >= B) {
        lead = lead && t == nreg && sfirst != bPrev && sfirst < B;
        mt = lead ? mt & (0 - mt) : 0; nt = 0; Kn = 0; own = false; odd = false;
    }
    odd = odd || ((mt != 0 || own) && sfirst + nt - bPrev >= NP) || (lead && (mt & ((1ull << (CH - R)) - 1)) == 0);
    float4 acc = make_float4(0, 0, 0, 0);
    auto pickup = [&](float4& c) {
        for (uint32_t mq = sw + OFF_M + h * 16, hh = h;;) {
            if (NS == 2 && hh == 0) { mq += 16; hh = 1; } else { mq += WB - (NS - 1) * 16; hh = 0; }
            mbar_wait0(mq);
            const uint32_t where = lds32(mq + 8);
            const float4 d = lds128((where & ~1u) + ll * 16);
            c.x += d.x; c.y += d.y; c.z += d.z; c.w += d.w;
            if (!(where & 1)) break;
        }
    };
    if (__builtin_expect(__any_sync(~0u, odd), 0)) {
        #pragma unroll
        for (int u = 0; u < F; u++) keep ^= r[u].x ^ r[u].y;
        if (B < 0) sts32(sw, keep);
        auto flush = [&](int b) { stg8_if(out + (size_t)b * 256 + lo, fin(acc, ldg8(out0 + (size_t)b * 256 + lo)), true); };
        if (wa + h == 0 && t < nreg) for (int e = 0; e < sfirst; e++) flush(e);
        float4 first = make_float4(0, 0, 0, 0);
        bool had = false;
        #pragma unroll 1
        for (int j = 0; j < CH; j += 4) {
            uint2 q[4];
            ldg2(q[0], q[1], lds128i(la + j * 8), lo);
            ldg2(q[2], q[3], lds128i(la + j * 8 + 16), lo);
            #pragma unroll
            for (int u = 0; u < 4; u++) {
                addrow(acc, q[u]);
                if ((mt >> (j + u + 1)) & 1) {
                    const int b = lds32(swin + 16 + (j + u) * 4), e = lds32(swin + 20 + (j + u) * 4);
                    if (lead) { first = acc; had = true; lead = false; } else flush(b);
                    acc = make_float4(0, 0, 0, 0);
                    if (t < nreg) {
                        #pragma unroll 1
                        for (int z = b + 1; z < e; z++) flush(z);
                    }
                }
            }
            __syncwarp();
        }
        if (lead && t == nreg) {
            const unsigned hm = NS == 1 ? ~0u : lane < 16 ? 0xffffu : 0xffff0000u;
            for (int q = wa + h * CH + CH + ll;; q += LPS) {
                const int s = q < nnz ? seg[q] : B, vv = q < nnz ? vals[q] : 0;
                const int n = __popc(__ballot_sync(hm, s == sfirst));
                #pragma unroll 4
                for (int z = 0; z < n; z++) addrow(acc, ldg8(table + (size_t)__shfl_sync(hm, vv, z, LPS) * 256 + lo));
                if (n < LPS) break;
            }
            first = acc; had = true; lead = false;
        }
        __syncwarp();
        const uint32_t cw = sw + lane * 16;
        if (had || lead) sts128(cw, had ? first : acc);
        if (had || lead) { if (ll == 0) sts32(sw + OFF_M + h * 16 + 8, cw | lead); mbar_arrive(sw + OFF_M + h * 16); }
        __syncwarp();
        if (own) { pickup(acc); flush(slast); }
        return;
    }

    uint32_t pk = sb + LL::OFF_P + (sfirst - bPrev) * PS + ll * 16;
    unsigned info = (Kn > 0 ? sfirst + lead - bPrev : 1) << 8 | Kn << 1 | own;
    if (w * NS + NS > nreg) {
        const int need = __ffsll(mt) - 1;
        const uint2 a0 = lds64(la);
        if (t == nreg) for (int i = max(need, F) + ll; i < CH; i += LPS) sts64(la + i * 8, a0);
        __syncwarp();
    }
    const uint32_t mbar = sw + OFF_M + h * 16;
    if (ll == 0) sts32(mbar + 8, pk);
    const unsigned mlo = (unsigned)mt, mhi = (unsigned)(mt >> 32);
    unsigned pend = lead ? pk : 0;
    auto arrive_if = [&]() {
        asm volatile("{ .reg .pred p, q; setp.ne.u32 q, %0, 0; setp.ne.and.u32 p, %2, %0, q; @p mbarrier.arrive.release.cta.shared::cta.b64 _, [%1]; @p mov.u32 %0, 0; }"
                     : "+r"(pend) : "r"(mbar), "r"(pk) : "memory");
    };
    uint2 y[gmax(1)];
    rounds<U, gmax(1), PS, 0>(acc, pk, mlo, mhi, r, y, la, lo, keep, zero, arrive_if);

    asm volatile("" : "+r"(info));
    const int slot0 = info >> 8;
    Kn = (info >> 1) & 127; own = info & 1;
    const unsigned gofs = (slot0 + lds32(sb + OFF_S + 12)) * 256 + lo;
    const uint32_t pbase = sb + LL::OFF_P + slot0 * PS + ll * 16;
    const uint32_t obase = sb + LL::OFF_O + (slot0 - 1) * OS + ll * 8;
    constexpr int SL = 12, FN = 6;
    #pragma unroll
    for (int q = 0; q < SL; q++) cp8_if(obase + q * OS, out0 + gofs + q * 256, q < Kn);
    cp_commit();
    float4 c; uint32_t where;
    {
        const uint32_t mq = NS == 2 ? mbar + (h ? WB - 16 : 16) : mbar + WB;
        asm volatile("{ .reg .pred p; .reg .b32 a;\n"
            "setp.ne.s32 p, %7, 0;\n"
            "mov.b32 %4, 1; mov.f32 %0, 0f00000000; mov.f32 %1, 0f00000000; mov.f32 %2, 0f00000000; mov.f32 %3, 0f00000000;\n"
            "@p mbarrier.test_wait.parity.acquire.cta.shared::cta.b64 p, [%5], 0;\n"
            "@p ld.shared.u32 %4, [%5+8];\n"
            "and.b32 a, %4, 0xfffffffe; add.u32 a, a, %6;\n"
            "@p ld.shared.v4.f32 {%0,%1,%2,%3}, [a]; }"
            : "=&f"(c.x), "=&f"(c.y), "=&f"(c.z), "=&f"(c.w), "=&r"(where) : "r"(mq), "r"(ll * 16), "r"((int)own) : "memory");
    }
    const bool extra = __any_sync(~0u, (own && (where & 1)) || Kn > SL || B < 0);
    keep ^= sched_fence();
    consume<U, gstart(kGroups - 2), gsize(kGroups - 2), 0, 0, PS>(acc, pk, mlo, mhi, r, 0, 0, keep, 0);
    keep ^= sched_fence();
    consume<gmax(1), gstart(kGroups - 1), gsize(kGroups - 1), 0, 0, PS>(acc, pk, mlo, mhi, y, 0, 0, keep, 0);
    if (__builtin_expect(extra, 0)) {
        if (B < 0) sts32(sw, keep);
        for (int q = SL; q < Kn; q++) cp8_if(obase + q * OS, out0 + (gofs + q * 256), true);
        if (own && (where & 1)) { c = make_float4(0, 0, 0, 0); pickup(c); }
        __syncwarp();
        cp_commit();
    }
    const bool inreg = own || ((mhi >> (CH - 32)) & 1);
    const int Kp = Kn - inreg;
    uint2 pp[FN], o[FN];
    #pragma unroll
    for (int q = 0; q < FN; q++) { const float4 x = lds128_if(pbase + q * PS, q < Kp); pp[q] = make_uint2(pack2(x.x, x.y), pack2(x.z, x.w)); }
    acc.x += c.x; acc.y += c.y; acc.z += c.z; acc.w += c.w;
    const uint2 pa = make_uint2(pack2(acc.x, acc.y), pack2(acc.z, acc.w));
    cp_wait0();
    const uint2 oa = lds64_if(obase + Kp * OS, inreg);
    #pragma unroll
    for (int q = 0; q < FN; q++) o[q] = lds64_if(obase + q * OS, q < Kp);
    stg8_if(out + (gofs + Kp * 256), make_uint2(addbf2(pa.x, oa.x), addbf2(pa.y, oa.y)), inreg);
    #pragma unroll
    for (int q = 0; q < FN; q++) stg8_if(out + gofs + q * 256, make_uint2(addbf2(pp[q].x, o[q].x), addbf2(pp[q].y, o[q].y)), q < Kp);
    #pragma unroll 1
    for (int q = FN; q < Kp; q++) stg8_if(out + (gofs + q * 256), fin(lds128(pbase + q * PS), lds64(obase + q * OS)), true);
}

__global__ void embag_simple_kernel(const int* vals, const int* seg, const char* table, int B, int nnz, const char* out0, char* out) {
    simple_bags(vals, seg, table, B, nnz, out0, out, (blockIdx.x * blockDim.x + threadIdx.x) >> 5, (gridDim.x * blockDim.x) >> 5);
}

constexpr int CH = 52, W = 28;
constexpr int NP2 = 304, NP1 = 168;

}

extern "C" void kernel_launch(void* const* d_in, const int* in_sizes, int n_in, void* d_out, int out_size) {
    const int* vals = (const int*)d_in[0];
    const int* seg = (const int*)d_in[1];
    const char* table = (const char*)d_in[2];
    const char* out0 = (const char*)d_in[3];
    const int nnz = in_sizes[0], B = out_size / 128;
    if (nnz < B / 4 || nnz == 0 || nnz > 0x7ff00000 || B >= (1 << 24) || ((uintptr_t)table & 255) || (((uintptr_t)vals | (uintptr_t)seg) & 15)) {
        embag_simple_kernel<<<1024, 256, 0, cudaStreamPerThread>>>(vals, seg, table, B, nnz, out0, (char*)d_out);
        return;
    }
    constexpr int smem1 = Layout<1, W - 1, CH, NP1>::TOTAL, smem2 = Layout<2, W - 1, CH, NP2>::TOTAL;
    static int sms = 0, split_ok = 0;
    if (!sms) {
        int dev = 0, coop = 0, per_sm = 0;
        cudaGetDevice(&dev);
        cudaDeviceGetAttribute(&coop, cudaDevAttrCooperativeLaunch, dev);
        cudaDeviceGetAttribute(&sms, cudaDevAttrMultiProcessorCount, dev);
        cudaFuncSetAttribute(embag_kernel<1, W, CH, NP1>, cudaFuncAttributeMaxDynamicSharedMemorySize, smem1);
        cudaFuncSetAttribute(embag_kernel<2, W, CH, NP2>, cudaFuncAttributeMaxDynamicSharedMemorySize, smem2);
        cudaOccupancyMaxActiveBlocksPerMultiprocessor(&per_sm, embag_kernel<2, W, CH, NP2>, W * 32, smem2);
        split_ok = coop && sms == kSplitSMs && per_sm == 1;
    }
    const int ns = (nnz + CH - 1) / CH;
    const unsigned nnz3 = nnz > 3 ? nnz - 3 : 0;
    if (split_ok && ns <= (2 * (W - 1) - 1) * (kSplitSMs / 2)) {
        const unsigned ratio = (unsigned)((((uint64_t)ns << 16) + kSplitSMs / 2 - 1) / (kSplitSMs / 2));
        cudaLaunchConfig_t cfg = {};
        cfg.gridDim = dim3(kSplitSMs); cfg.blockDim = dim3(W * 32); cfg.dynamicSmemBytes = smem2; cfg.stream = cudaStreamPerThread;
        cudaLaunchAttribute at[1];
        at[0].id = cudaLaunchAttributeCooperative; at[0].val.cooperative = 1;
        cfg.attrs = at; cfg.numAttrs = 1;
        cudaLaunchKernelEx(&cfg, embag_kernel<2, W, CH, NP2>, vals, seg, nnz3 * 4, ratio, table, B, nnz, out0, (char*)d_out, 0u);
    } else {
        int G = (ns + W - 3) / (W - 2);
        if (G < sms) G = sms;
        const unsigned ratio = (unsigned)((((uint64_t)ns << 16) + G - 1) / G);
        embag_kernel<1, W, CH, NP1><<<G, W * 32, smem1, cudaStreamPerThread>>>(vals, seg, nnz3, ratio, table, B, nnz, out0, (char*)d_out, 0u);
    }
}
```
